```python
import torch

def _softmax(x, axis=-1):
    return torch.softmax(x, dim=axis)
def _gelu(x):
    return torch.nn.functional.gelu(x, approximate="tanh")
def _silu(x):
    return torch.nn.functional.silu(x)
def _sigmoid(x):
    return torch.sigmoid(x)
def _layernorm(x, axis=-1, eps=1e-5):
    m = x.mean(dim=axis, keepdim=True)
    v = x.var(dim=axis, keepdim=True, unbiased=False)
    return (x - m) / torch.sqrt(v + eps)
def _scatter_add(tgt, idx, src, axis=0):
    return tgt.clone().index_add_(axis, idx, src)
def _segment_sum(src, seg, n):
    out = torch.zeros((n,) + src.shape[1:], dtype=src.dtype)
    return out.index_add_(0, seg, src)
def _pad(x, pw):
    flat = tuple(v for pair in reversed(pw) for v in pair)
    return torch.nn.functional.pad(x, flat)

kernel_name = 'sequential_preLN__sliding_local_dilated__dense_activation_relu__prompt'

def setup_inputs():

    _w = (lambda a: (lambda t: t.to(torch.bfloat16) if t.is_floating_point() else t)(torch.as_tensor(a)))
    def _A_setup():
        B, S, D = 1, 2048, 448
        return {
            "x": _w((lambda *s: torch.randn(*s, dtype=torch.bfloat16) * 0.05)(B, S, D)),
            "wqkv": _w((lambda *s: torch.randn(*s, dtype=torch.bfloat16) * 0.05)(D, 3 * D)),
            "wo": _w((lambda *s: torch.randn(*s, dtype=torch.bfloat16) * 0.05)(D, D)),
        }
    _A_in = _A_setup()

    def _B_setup():
        B, S, D, Dff = 1, 2048, 448, 1792
        return {
            "x": _w((lambda *s: torch.randn(*s, dtype=torch.bfloat16) * 0.05)(B, S, D)),
            "w1": _w((lambda *s: torch.randn(*s, dtype=torch.bfloat16) * 0.05)(D, Dff)),
            "w2": _w((lambda *s: torch.randn(*s, dtype=torch.bfloat16) * 0.05)(Dff, D)),
        }
    _B_in = _B_setup()

    return {
        "A_x": _A_in["x"],
        "A_wqkv": _A_in["wqkv"],
        "A_wo": _A_in["wo"],
        "B_x": _B_in["x"],
        "B_w1": _B_in["w1"],
        "B_w2": _B_in["w2"],
    }

def reference(A_x, A_wqkv, A_wo, B_x, B_w1, B_w2):
    def _A_ref(x, wqkv, wo):
        B, S, D = x.shape
        H = 16; Dh = D // H
        W, dil = 8, 2
        qkv = (lambda x, *d: x.permute(*d))((x @ wqkv).reshape(B, S, 3, H, Dh), 2, 0, 3, 1, 4)
        q, k, v = qkv[0], qkv[1], qkv[2]
        scale = Dh ** -0.5
        pos = torch.arange(S)
        off = torch.arange(W) * dil
        idx = pos[:, None] - off[None, :]
        mask = idx >= 0
        idx_c = torch.where(mask, idx, 0).reshape(-1)
        kg = k[:, :, idx_c, :].reshape(B, H, S, W, Dh)
        vg = v[:, :, idx_c, :].reshape(B, H, S, W, Dh)
        logits = torch.einsum("bhsd,bhswd->bhsw", q, kg) * scale
        logits = torch.where(mask[None, None, :, :], logits, -1e9)
        attn = _softmax(logits, axis=-1)
        o = torch.einsum("bhsw,bhswd->bhsd", attn, vg)
        return (lambda x, *d: x.permute(*d))(o, 0, 2, 1, 3).reshape(B, S, D) @ wo

    def _B_ref(x, w1, w2):
        h = torch.einsum("bsd,df->bsf", x, w1)
        zero = torch.zeros_like(h)
        h = torch.maximum(h, zero)
        return torch.einsum("bsf,fd->bsd", h, w2)

    x = A_x
    h = x + _A_ref(_layernorm(x, axis=-1), A_wqkv, A_wo)
    h2 = h + _B_ref(_layernorm(h, axis=-1), B_w1, B_w2)
    return h2
```

```cpp
#include <cuda_runtime.h>
#include <cuda_bf16.h>
#include <cuda.h>
#include <stdint.h>

namespace {

constexpr int DM = 448, NQKV = 1344, DFF = 1792;
constexpr int GRID = 128;
constexpr int UNIT = 14336;
constexpr int STAGE = 2 * UNIT;
constexpr int NSTAGE = 6;
constexpr int XATOM = 8192;
constexpr int STG_BYTES = 7168;

constexpr int OFF_STG = NSTAGE * STAGE;
constexpr int OFF_XB = 4 * STAGE;
constexpr int OFF_BAR = OFF_STG + 8 * STG_BYTES;
constexpr int BAR_FULL = 0, BAR_EMPTY = 6, BAR_STG = 12, BAR_X = 20, BAR_XREAD = 34;
constexpr int NBAR = 35;
constexpr int SMEM_BYTES = OFF_BAR + NBAR * 8 + 1024;

constexpr int W_AFTER = 2;
constexpr int ODD_DELAY = 1400;
constexpr int FETCH_DELAY_O = 1100;
constexpr int FETCH_DELAY_H = 1150;
constexpr int FETCH_DELAY_S = 1200;

constexpr float LN_EPS = 1e-5f;
constexpr int SPIN_LIMIT = 1 << 17;

__device__ uint4 g_x1[16 * 2 * 4 * 28 * 32];
__device__ uint4 g_x2[16 * 2 * 4 * 28 * 32];
__device__ uint4 g_x3[16 * 2 * 4 * 7 * 8 * 128];
__device__ uint4 g_halo[16 * 2 * 8 * 128];
__device__ uint4 g_st2[16 * 2 * 7 * 4 * 8];
__device__ uint32_t g_hint1[16 * 2 * 4 * 8];
__device__ uint32_t g_hint2[16 * 2 * 4 * 8];
__device__ uint32_t g_epoch[GRID];

__device__ __forceinline__ uint32_t smem_u32(const void* p) { return (uint32_t)__cvta_generic_to_shared(p); }
__device__ __forceinline__ void mbar_init(uint32_t bar, uint32_t cnt) {
    asm volatile("mbarrier.init.shared::cta.b64 [%0], %1;" ::"r"(bar), "r"(cnt) : "memory");
}
__device__ __forceinline__ void mbar_expect_tx(uint32_t bar, uint32_t bytes) {
    asm volatile("mbarrier.arrive.expect_tx.shared::cta.b64 _, [%0], %1;" ::"r"(bar), "r"(bytes) : "memory");
}
__device__ __forceinline__ void mbar_arrive(uint32_t bar) {
    asm volatile("mbarrier.arrive.shared::cta.b64 _, [%0];" ::"r"(bar) : "memory");
}
__device__ __forceinline__ void mbar_wait(uint32_t bar, uint32_t parity) {
    asm volatile("{\n.reg .pred p;\n.reg .u32 n;\nmov.u32 n, 0;\n"
                 "WAIT_%=:\nmbarrier.try_wait.parity.shared::cta.b64 p, [%0], %1;\n@p bra DONE_%=;\n"
                 "add.u32 n, n, 1;\nsetp.lt.u32 p, n, %2;\n@p bra WAIT_%=;\nDONE_%=:\n}"
                 ::"r"(bar), "r"(parity), "n"(SPIN_LIMIT) : "memory");
}
__device__ __forceinline__ void tma2d(uint32_t dst, const CUtensorMap* m, int c0, int c1, uint32_t bar) {
    asm volatile("cp.async.bulk.tensor.2d.shared::cluster.global.mbarrier::complete_tx::bytes [%0], [%1, {%3, %4}], [%2];"
                 ::"r"(dst), "l"(m), "r"(bar), "r"(c0), "r"(c1) : "memory");
}
__device__ __forceinline__ void bulk_load(uint32_t dst, const void* src, uint32_t bytes, uint32_t bar) {
    asm volatile("cp.async.bulk.shared::cluster.global.mbarrier::complete_tx::bytes [%0], [%1], %2, [%3];"
                 ::"r"(dst), "l"(src), "r"(bytes), "r"(bar) : "memory");
}
__device__ __forceinline__ void sts128(uint32_t addr, uint32_t a, uint32_t b, uint32_t c, uint32_t d) {
    asm volatile("st.shared.v4.u32 [%0], {%1, %2, %3, %4};" ::"r"(addr), "r"(a), "r"(b), "r"(c), "r"(d) : "memory");
}
__device__ __forceinline__ uint4 lds128(uint32_t addr) {
    uint4 v;
    asm volatile("ld.shared.v4.u32 {%0, %1, %2, %3}, [%4];" : "=r"(v.x), "=r"(v.y), "=r"(v.z), "=r"(v.w) : "r"(addr) : "memory");
    return v;
}
__device__ __forceinline__ void tma3d_local(uint32_t dst, const CUtensorMap* m, int c0, int c1, int c2, uint32_t bar) {
    asm volatile("cp.async.bulk.tensor.3d.shared::cluster.global.mbarrier::complete_tx::bytes [%0], [%1, {%3, %4, %5}], [%2];"
                 ::"r"(dst), "l"(m), "r"(bar), "r"(c0), "r"(c1), "r"(c2) : "memory");
}
__device__ __forceinline__ void prefetch_map(const CUtensorMap* m) {
    asm volatile("prefetch.tensormap [%0];" ::"l"(m) : "memory");
}
__device__ __forceinline__ uint4 ld_ll(const uint4* p) {
    uint4 v;
    asm volatile("{\n.reg .b128 r;\n.reg .b64 x, y;\nld.relaxed.gpu.global.b128 r, [%4];\nmov.b128 {x, y}, r;\n"
                 "mov.b64 {%0, %1}, x;\nmov.b64 {%2, %3}, y;\n}"
                 : "=r"(v.x), "=r"(v.y), "=r"(v.z), "=r"(v.w) : "l"(p) : "memory");
    return v;
}
__device__ __forceinline__ void st_ll(uint4* p, uint32_t a, uint32_t b, uint32_t c, uint32_t d) {
    asm volatile("{\n.reg .b128 r;\n.reg .b64 x, y;\nmov.b64 x, {%0, %1};\nmov.b64 y, {%2, %3};\nmov.b128 r, {x, y};\n"
                 "st.relaxed.gpu.global.b128 [%4], r;\n}"
                 ::"r"(a), "r"(b), "r"(c), "r"(d), "l"(p) : "memory");
}
__device__ __forceinline__ void st_ll8(void* p, uint32_t a, uint32_t b) {
    asm volatile("{\n.reg .b64 x;\nmov.b64 x, {%0, %1};\nst.relaxed.gpu.global.b64 [%2], x;\n}" ::"r"(a), "r"(b), "l"(p) : "memory");
}
__device__ __forceinline__ uint32_t ld_rlx(const uint32_t* p) {
    uint32_t v;
    asm volatile("ld.relaxed.gpu.global.u32 %0, [%1];" : "=r"(v) : "l"(p) : "memory");
    return v;
}
__device__ __forceinline__ void st_rlx(uint32_t* p, uint32_t v) {
    asm volatile("st.relaxed.gpu.global.u32 [%0], %1;" ::"l"(p), "r"(v) : "memory");
}
__device__ __forceinline__ void ldsm4(uint32_t (&r)[4], uint32_t addr) {
    asm volatile("ldmatrix.sync.aligned.m8n8.x4.shared.b16 {%0, %1, %2, %3}, [%4];"
                 : "=r"(r[0]), "=r"(r[1]), "=r"(r[2]), "=r"(r[3]) : "r"(addr) : "memory");
}
__device__ __forceinline__ void stsm4(uint32_t addr, uint32_t a, uint32_t b, uint32_t c, uint32_t d) {
    asm volatile("stmatrix.sync.aligned.m8n8.x4.shared.b16 [%0], {%1, %2, %3, %4};"
                 ::"r"(addr), "r"(a), "r"(b), "r"(c), "r"(d) : "memory");
}
__device__ __forceinline__ uint32_t movtrans(uint32_t a) {
    uint32_t d;
    asm volatile("movmatrix.sync.aligned.m8n8.trans.b16 %0, %1;" : "=r"(d) : "r"(a));
    return d;
}
__device__ __forceinline__ void mma16816(float (&c)[4], uint32_t a0, uint32_t a1, uint32_t a2, uint32_t a3,
                                         uint32_t b0, uint32_t b1) {
    asm volatile("mma.sync.aligned.m16n8k16.row.col.f32.bf16.bf16.f32 {%0, %1, %2, %3}, {%4, %5, %6, %7}, {%8, %9}, {%0, %1, %2, %3};"
                 : "+f"(c[0]), "+f"(c[1]), "+f"(c[2]), "+f"(c[3])
                 : "r"(a0), "r"(a1), "r"(a2), "r"(a3), "r"(b0), "r"(b1));
}
__device__ __forceinline__ void mma1688(float (&c)[4], uint32_t a0, uint32_t a1, uint32_t b0) {
    asm volatile("mma.sync.aligned.m16n8k8.row.col.f32.bf16.bf16.f32 {%0, %1, %2, %3}, {%4, %5}, {%6}, {%0, %1, %2, %3};"
                 : "+f"(c[0]), "+f"(c[1]), "+f"(c[2]), "+f"(c[3]) : "r"(a0), "r"(a1), "r"(b0));
}
__device__ __forceinline__ uint32_t pack_bf16(float lo, float hi) {
    uint32_t r;
    asm("cvt.rn.bf16x2.f32 %0, %1, %2;" : "=r"(r) : "f"(hi), "f"(lo));
    return r;
}
__device__ __forceinline__ uint32_t pack_relu_bf16(float lo, float hi) {
    uint32_t r;
    asm("cvt.rn.relu.bf16x2.f32 %0, %1, %2;" : "=r"(r) : "f"(hi), "f"(lo));
    return r;
}
__device__ __forceinline__ uint32_t fma_bf16x2(uint32_t a, uint32_t b, uint32_t c) {
    uint32_t d;
    asm("fma.rn.bf16x2 %0, %1, %2, %3;" : "=r"(d) : "r"(a), "r"(b), "r"(c));
    return d;
}
__device__ __forceinline__ float ex2(float x) {
    float y;
    asm("ex2.approx.ftz.f32 %0, %1;" : "=f"(y) : "f"(x));
    return y;
}
__device__ __forceinline__ float rsqrt_pos(float x) {
    float y;
    asm("rsqrt.approx.ftz.f32 %0, %1;" : "=f"(y) : "f"(x));
    return y;
}
__device__ __forceinline__ float bf_lo(uint32_t v) { return __uint_as_float(v << 16); }
__device__ __forceinline__ float bf_hi(uint32_t v) { return __uint_as_float(v & 0xffff0000u); }
__device__ __forceinline__ uint32_t tag_miss(uint32_t acc, uint32_t v, uint32_t tag) {
    uint32_t r;
    asm("lop3.b32 %0, %1, %2, %3, 0xF6;" : "=r"(r) : "r"(acc), "r"(v), "r"(tag));
    return r;
}
__device__ __forceinline__ uint32_t set_tag(uint32_t v, uint32_t tag) { return (v & ~1u) | tag; }

__device__ __forceinline__ void wg_fence() { asm volatile("wgmma.fence.sync.aligned;" ::: "memory"); }
__device__ __forceinline__ void wg_commit() { asm volatile("wgmma.commit_group.sync.aligned;" ::: "memory"); }
template <int N> __device__ __forceinline__ void wg_wait() {
    asm volatile("wgmma.wait_group.sync.aligned %0;" ::"n"(N) : "memory");
}
template <int N> __device__ __forceinline__ void keep_regs(float (&d)[N]) {
#pragma unroll
    for (int i = 0; i < N; i++) asm volatile("" : "+f"(d[i])::"memory");
}
__device__ __forceinline__ uint64_t make_desc(uint32_t addr) {
    return (uint64_t)((addr & 0x3FFFF) >> 4) | ((uint64_t)(UNIT >> 4) << 16) | ((uint64_t)(1024 >> 4) << 32) | (1ull << 62);
}
__device__ __forceinline__ void bar_arrive(int id, int cnt) { asm volatile("bar.arrive %0, %1;" ::"r"(id), "r"(cnt) : "memory"); }
__device__ __forceinline__ void bar_sync(int id, int cnt) { asm volatile("bar.sync %0, %1;" ::"r"(id), "r"(cnt) : "memory"); }

__device__ __forceinline__ void wgmma_rs_n56(float (&d)[28], uint32_t a0, uint32_t a1, uint32_t a2, uint32_t a3, uint64_t descB, int scaleD) {
    asm volatile("{\n.reg .pred p;\nsetp.ne.b32 p, %33, 0;\n"
        "wgmma.mma_async.sync.aligned.m64n56k16.f32.bf16.bf16 "
        "{%0, %1, %2, %3, %4, %5, %6, %7, %8, %9, %10, %11, %12, %13, %14, %15, "
        "%16, %17, %18, %19, %20, %21, %22, %23, %24, %25, %26, %27}, "
        "{%28, %29, %30, %31}, %32, p, 1, 1, 1;\n}"
        : "+f"(d[0]), "+f"(d[1]), "+f"(d[2]), "+f"(d[3]), "+f"(d[4]), "+f"(d[5]), "+f"(d[6]), "+f"(d[7]),
          "+f"(d[8]), "+f"(d[9]), "+f"(d[10]), "+f"(d[11]), "+f"(d[12]), "+f"(d[13]), "+f"(d[14]), "+f"(d[15]),
          "+f"(d[16]), "+f"(d[17]), "+f"(d[18]), "+f"(d[19]), "+f"(d[20]), "+f"(d[21]), "+f"(d[22]), "+f"(d[23]),
          "+f"(d[24]), "+f"(d[25]), "+f"(d[26]), "+f"(d[27])
        : "r"(a0), "r"(a1), "r"(a2), "r"(a3), "l"(descB), "r"(scaleD));
}
__device__ __forceinline__ void wgmma_rs_n64(float (&d)[32], uint32_t a0, uint32_t a1, uint32_t a2, uint32_t a3, uint64_t descB, int scaleD) {
    asm volatile("{\n.reg .pred p;\nsetp.ne.b32 p, %37, 0;\n"
        "wgmma.mma_async.sync.aligned.m64n64k16.f32.bf16.bf16 "
        "{%0, %1, %2, %3, %4, %5, %6, %7, %8, %9, %10, %11, %12, %13, %14, %15, "
        "%16, %17, %18, %19, %20, %21, %22, %23, %24, %25, %26, %27, %28, %29, %30, %31}, "
        "{%32, %33, %34, %35}, %36, p, 1, 1, 1;\n}"
        : "+f"(d[0]), "+f"(d[1]), "+f"(d[2]), "+f"(d[3]), "+f"(d[4]), "+f"(d[5]), "+f"(d[6]), "+f"(d[7]),
          "+f"(d[8]), "+f"(d[9]), "+f"(d[10]), "+f"(d[11]), "+f"(d[12]), "+f"(d[13]), "+f"(d[14]), "+f"(d[15]),
          "+f"(d[16]), "+f"(d[17]), "+f"(d[18]), "+f"(d[19]), "+f"(d[20]), "+f"(d[21]), "+f"(d[22]), "+f"(d[23]),
          "+f"(d[24]), "+f"(d[25]), "+f"(d[26]), "+f"(d[27]), "+f"(d[28]), "+f"(d[29]), "+f"(d[30]), "+f"(d[31])
        : "r"(a0), "r"(a1), "r"(a2), "r"(a3), "l"(descB), "r"(scaleD));
}
__device__ __forceinline__ void wgmma_rs_n96(float (&d)[48], uint32_t a0, uint32_t a1, uint32_t a2, uint32_t a3, uint64_t descB, int scaleD) {
    asm volatile("{\n.reg .pred p;\nsetp.ne.b32 p, %53, 0;\n"
        "wgmma.mma_async.sync.aligned.m64n96k16.f32.bf16.bf16 "
        "{%0, %1, %2, %3, %4, %5, %6, %7, %8, %9, %10, %11, %12, %13, %14, %15, "
        "%16, %17, %18, %19, %20, %21, %22, %23, %24, %25, %26, %27, %28, %29, %30, %31, "
        "%32, %33, %34, %35, %36, %37, %38, %39, %40, %41, %42, %43, %44, %45, %46, %47}, "
        "{%48, %49, %50, %51}, %52, p, 1, 1, 1;\n}"
        : "+f"(d[0]), "+f"(d[1]), "+f"(d[2]), "+f"(d[3]), "+f"(d[4]), "+f"(d[5]), "+f"(d[6]), "+f"(d[7]),
          "+f"(d[8]), "+f"(d[9]), "+f"(d[10]), "+f"(d[11]), "+f"(d[12]), "+f"(d[13]), "+f"(d[14]), "+f"(d[15]),
          "+f"(d[16]), "+f"(d[17]), "+f"(d[18]), "+f"(d[19]), "+f"(d[20]), "+f"(d[21]), "+f"(d[22]), "+f"(d[23]),
          "+f"(d[24]), "+f"(d[25]), "+f"(d[26]), "+f"(d[27]), "+f"(d[28]), "+f"(d[29]), "+f"(d[30]), "+f"(d[31]),
          "+f"(d[32]), "+f"(d[33]), "+f"(d[34]), "+f"(d[35]), "+f"(d[36]), "+f"(d[37]), "+f"(d[38]), "+f"(d[39]),
          "+f"(d[40]), "+f"(d[41]), "+f"(d[42]), "+f"(d[43]), "+f"(d[44]), "+f"(d[45]), "+f"(d[46]), "+f"(d[47])
        : "r"(a0), "r"(a1), "r"(a2), "r"(a3), "l"(descB), "r"(scaleD));
}
__device__ __forceinline__ void wgmma_rs_n128(float (&d)[64], uint32_t a0, uint32_t a1, uint32_t a2, uint32_t a3, uint64_t descB, int scaleD) {
    asm volatile("{\n.reg .pred p;\nsetp.ne.b32 p, %69, 0;\n"
        "wgmma.mma_async.sync.aligned.m64n128k16.f32.bf16.bf16 "
        "{%0, %1, %2, %3, %4, %5, %6, %7, %8, %9, %10, %11, %12, %13, %14, %15, "
        "%16, %17, %18, %19, %20, %21, %22, %23, %24, %25, %26, %27, %28, %29, %30, %31, "
        "%32, %33, %34, %35, %36, %37, %38, %39, %40, %41, %42, %43, %44, %45, %46, %47, "
        "%48, %49, %50, %51, %52, %53, %54, %55, %56, %57, %58, %59, %60, %61, %62, %63}, "
        "{%64, %65, %66, %67}, %68, p, 1, 1, 1;\n}"
        : "+f"(d[0]), "+f"(d[1]), "+f"(d[2]), "+f"(d[3]), "+f"(d[4]), "+f"(d[5]), "+f"(d[6]), "+f"(d[7]),
          "+f"(d[8]), "+f"(d[9]), "+f"(d[10]), "+f"(d[11]), "+f"(d[12]), "+f"(d[13]), "+f"(d[14]), "+f"(d[15]),
          "+f"(d[16]), "+f"(d[17]), "+f"(d[18]), "+f"(d[19]), "+f"(d[20]), "+f"(d[21]), "+f"(d[22]), "+f"(d[23]),
          "+f"(d[24]), "+f"(d[25]), "+f"(d[26]), "+f"(d[27]), "+f"(d[28]), "+f"(d[29]), "+f"(d[30]), "+f"(d[31]),
          "+f"(d[32]), "+f"(d[33]), "+f"(d[34]), "+f"(d[35]), "+f"(d[36]), "+f"(d[37]), "+f"(d[38]), "+f"(d[39]),
          "+f"(d[40]), "+f"(d[41]), "+f"(d[42]), "+f"(d[43]), "+f"(d[44]), "+f"(d[45]), "+f"(d[46]), "+f"(d[47]),
          "+f"(d[48]), "+f"(d[49]), "+f"(d[50]), "+f"(d[51]), "+f"(d[52]), "+f"(d[53]), "+f"(d[54]), "+f"(d[55]),
          "+f"(d[56]), "+f"(d[57]), "+f"(d[58]), "+f"(d[59]), "+f"(d[60]), "+f"(d[61]), "+f"(d[62]), "+f"(d[63])
        : "r"(a0), "r"(a1), "r"(a2), "r"(a3), "l"(descB), "r"(scaleD));
}

__device__ __forceinline__ void wait_hints(const uint32_t* words, int n, uint32_t epoch, int lane) {
#pragma unroll 1
    for (int it = 0; it < SPIN_LIMIT; it++) {
        const bool ok = (lane >= n) || (ld_rlx(words + lane) == epoch);
        if (__all_sync(0xffffffffu, ok)) break;
    }
}
template <int N, int STRIDE>
__device__ __forceinline__ void validate(uint4 (&v)[N], const uint4* src, uint32_t tag) {
#pragma unroll 1
    for (int it = 0; it < SPIN_LIMIT; it++) {
        uint32_t bad = 0;
#pragma unroll
        for (int i = 0; i < N; i++) bad = tag_miss(bad, v[i].x, tag);
        if (__all_sync(0xffffffffu, (bad & 1u) == 0)) break;
#pragma unroll
        for (int i = 0; i < N; i++) v[i] = ld_ll(src + i * STRIDE);
    }
}
struct Stager {
    uint32_t buf, bar, phase;
    int lane;
    __device__ __forceinline__ void fetch(const uint4* src, uint32_t bytes) const {
        if (lane == 0) { mbar_expect_tx(bar, bytes); bulk_load(buf, src, bytes, bar); }
    }
    __device__ __forceinline__ void fetch2(const uint4* a, const uint4* b) const {
        if (lane == 0) { mbar_expect_tx(bar, 4096); bulk_load(buf, a, 2048, bar); bulk_load(buf + 2048, b, 2048, bar); }
    }
    template <int FIRST, int N, uint32_t HALVES, int TOT>
    __device__ __forceinline__ bool take(uint4 (&v)[TOT], uint32_t tag) {
        mbar_wait(bar, phase);
        phase ^= 1;
        uint32_t bad = 0;
#pragma unroll
        for (int i = 0; i < N; i++) {
            v[FIRST + i] = lds128(buf + i * 512 + lane * 16);
            bad = tag_miss(bad, v[FIRST + i].x, tag);
            if ((HALVES >> i) & 1) bad = tag_miss(bad, v[FIRST + i].z, tag);
        }
        return __all_sync(0xffffffffu, (bad & 1u) == 0);
    }
    template <int FIRST, int N, uint32_t HALVES, int NH = 0, int TOT>
    __device__ __forceinline__ void take_retry(uint4 (&v)[TOT], const uint4* src, uint32_t tag,
                                               const uint32_t* hints = nullptr, uint32_t epoch = 0) {
#pragma unroll 1
        for (int it = 0; it < SPIN_LIMIT; it++) {
            if (take<FIRST, N, HALVES>(v, tag)) break;
            if (NH > 0) wait_hints(hints, NH, epoch, lane);
            fetch(src, N * 512);
        }
    }
};
__device__ __forceinline__ void accum_stats(const uint4 (&r)[4], float& s0, float& q0, float& s1, float& q1) {
#pragma unroll
    for (int m = 0; m < 4; m++) {
        float a, b;
        a = bf_lo(r[m].x); b = bf_hi(r[m].x); s0 += a + b; q0 = fmaf(a, a, fmaf(b, b, q0));
        a = bf_lo(r[m].y); b = bf_hi(r[m].y); s1 += a + b; q1 = fmaf(a, a, fmaf(b, b, q1));
        a = bf_lo(r[m].z); b = bf_hi(r[m].z); s0 += a + b; q0 = fmaf(a, a, fmaf(b, b, q0));
        a = bf_lo(r[m].w); b = bf_hi(r[m].w); s1 += a + b; q1 = fmaf(a, a, fmaf(b, b, q1));
    }
}
__device__ __forceinline__ void quad_reduce(float& s0, float& q0, float& s1, float& q1) {
#pragma unroll
    for (int o = 1; o <= 2; o <<= 1) {
        s0 += __shfl_xor_sync(0xffffffffu, s0, o);
        q0 += __shfl_xor_sync(0xffffffffu, q0, o);
        s1 += __shfl_xor_sync(0xffffffffu, s1, o);
        q1 += __shfl_xor_sync(0xffffffffu, q1, o);
    }
}
__device__ __forceinline__ void stats_to_scale(float s0, float q0, float s1, float q1,
                                               float& rs0, float& mr0, float& rs1, float& mr1) {
    const float m0 = s0 * (1.0f / DM), m1 = s1 * (1.0f / DM);
    rs0 = rsqrt_pos(fmaxf(q0 * (1.0f / DM) - m0 * m0, 0.0f) + LN_EPS);
    rs1 = rsqrt_pos(fmaxf(q1 * (1.0f / DM) - m1 * m1, 0.0f) + LN_EPS);
    mr0 = -m0 * rs0;
    mr1 = -m1 * rs1;
}
__device__ __forceinline__ void finish_stats(uint4 (&v)[7], const uint4* src, uint32_t tag3,
                                             float& rs0, float& mr0, float& rs1, float& mr1) {
#pragma unroll 1
    for (int it = 0; it < SPIN_LIMIT; it++) {
        uint32_t bad = 0;
#pragma unroll
        for (int i = 0; i < 7; i++) bad = tag_miss(bad, v[i].x, tag3);
        if (__all_sync(0xffffffffu, (bad & 3u) == 0)) break;
#pragma unroll
        for (int i = 0; i < 7; i++) v[i] = ld_ll(src + i * 32);
    }
    float s0 = 0.f, q0 = 0.f, s1 = 0.f, q1 = 0.f;
#pragma unroll
    for (int i = 0; i < 7; i++) {
        s0 += __uint_as_float(v[i].x); q0 += __uint_as_float(v[i].y);
        s1 += __uint_as_float(v[i].z); q1 += __uint_as_float(v[i].w);
    }
    stats_to_scale(s0, q0, s1, q1, rs0, mr0, rs1, mr1);
}
struct RowScale {
    uint32_t hi, lo, mr;
    __device__ __forceinline__ void set(float rs, float m) {
        hi = pack_bf16(rs, rs);
        const float r = rs - bf_lo(hi);
        lo = pack_bf16(r, r);
        mr = pack_bf16(m, m);
    }
    __device__ __forceinline__ uint32_t apply(uint32_t v) const { return fma_bf16x2(v, hi, fma_bf16x2(v, lo, mr)); }
};

}

__global__ void __launch_bounds__(384, 1)
fused_block_kernel(const __grid_constant__ CUtensorMap m_x, const __grid_constant__ CUtensorMap m_qkv,
                   const __grid_constant__ CUtensorMap m_wo, const __grid_constant__ CUtensorMap m_w1,
                   const __grid_constant__ CUtensorMap m_w1h, const __grid_constant__ CUtensorMap m_w2a,
                   const __grid_constant__ CUtensorMap m_w2b, __nv_bfloat16* __restrict__ out) {
    extern __shared__ uint8_t smem_raw[];
    const uint32_t sraw = smem_u32(smem_raw);
    const uint32_t sbase = (sraw + 1023u) & ~1023u;
    const uint32_t bars = sbase + OFF_BAR;

    const int tid = threadIdx.x, wg = tid >> 7, warp = tid >> 5, lane = tid & 31;
    const int b = blockIdx.x;
    const int j = b & 7;
    const int g = b >> 3;
    const int gp = g >> 1;
    const int hid_a = 224 * j + ((j & 1) ? 32 : 0);
    const int hid_h = 224 * j + ((j & 1) ? 0 : 192);
    const int nstage = (j < 7) ? 23 : 21;
    if (warp == 9) {
        if (lane == 0) {
            prefetch_map(&m_x);
#pragma unroll
            for (int i = 0; i < 14; i++) mbar_init(bars + 8 * (BAR_X + i), 1);
            asm volatile("fence.mbarrier_init.release.cluster;" ::: "memory");
        }
        __syncwarp();
        bar_arrive(0, 384);
    } else {
        if (tid == 256) {
            prefetch_map(&m_qkv);
#pragma unroll
            for (int i = 0; i < NSTAGE; i++) {
                mbar_init(bars + 8 * (BAR_FULL + i), 1);
                mbar_init(bars + 8 * (BAR_EMPTY + i), 8);
            }
#pragma unroll
            for (int i = 0; i < 8; i++) mbar_init(bars + 8 * (BAR_STG + i), 1);
            mbar_init(bars + 8 * BAR_XREAD, 4);
            asm volatile("fence.mbarrier_init.release.cluster;" ::: "memory");
        }
        __syncwarp();
        bar_sync(0, 384);
    }
    auto release = [&](int s) {
        __syncwarp();
        if (lane == 0) mbar_arrive(bars + 8 * (BAR_EMPTY + s));
    };

    if (__builtin_expect(wg == 2, 0)) {
        asm volatile("setmaxnreg.dec.sync.aligned.u32 24;");
        if (lane != 0) return;
        if (warp == 8) {
            int slot = 0, use = 0;
#pragma unroll 1
            for (int n = 0; n < nstage; n++) {
                const int prior = use + (slot >= 4 ? 1 : 0);
                if (prior > 0) mbar_wait(bars + 8 * (BAR_EMPTY + slot), (prior - 1) & 1);
                if (n == 0) mbar_wait(bars + 8 * (BAR_X + W_AFTER), 0);
                const uint32_t full = bars + 8 * (BAR_FULL + slot);
                const uint32_t dst = sbase + slot * STAGE;
                const int s = (j < 7 || n < 6) ? n : n + 2;
                mbar_expect_tx(full, s < 6 ? 2 * 112 * 112 : ((s >= 12 && s < 16) ? UNIT + UNIT / 2 : STAGE));
#pragma unroll 1
                for (int half = 0; half < 2; half++) {
                    const CUtensorMap* map;
                    int c0, c1;
                    uint32_t off = half * UNIT;
                    if (s < 6) { map = &m_qkv; c0 = (s < 4 ? 448 * (1 + (s >> 1)) : 0) + 56 * j; c1 = 224 * (s & 1) + 112 * half; }
                    else if (s < 8) { map = &m_wo; c0 = 64 * j; c1 = 224 * (s - 6) + 112 * half; }
                    else if (s < 12) { map = &m_w1; c0 = hid_a + 64 * half; c1 = 112 * (s - 8); }
                    else if (s < 16) { map = half ? &m_w1h : &m_w1; c0 = half ? hid_h : hid_a + 128; c1 = 112 * (s - 12); }
                    else {
                        const int pss = s - 16;
                        c0 = 64 * ((j < 7) ? (j + 1 + pss) % 7 : (gp + pss) % 7);
                        if (half == 0) tma2d(dst + 192 * 128, &m_w2b, c0, hid_h, full);
                        map = &m_w2a; c1 = hid_a + 96 * half; off = half * 96 * 128;
                    }
                    tma2d(dst + off, map, c0, c1, full);
                }
                if (n == 0) {
                    prefetch_map(&m_wo); prefetch_map(&m_w1); prefetch_map(&m_w1h);
                    prefetch_map(&m_w2a); prefetch_map(&m_w2b);
                }
                if (++slot == NSTAGE) { slot = 0; use++; }
            }
        } else if (warp == 9) {
#pragma unroll 1
            for (int i = 0; i < 14; i++) {
                const int par = i >= 7 ? 1 : 0, a = i - 7 * par;
                const uint32_t bar = bars + 8 * (BAR_X + i);
                mbar_expect_tx(bar, XATOM);
                tma3d_local(sbase + (par ? OFF_XB : OFF_STG) + a * XATOM, &m_x, 64 * a, 64 * g, par, bar);
            }
        }
        return;
    }

    uint32_t epoch_raw;
    asm volatile("ld.global.u32 %0, [%1];" : "=r"(epoch_raw) : "l"(&g_epoch[b]) : "memory");
    asm volatile("setmaxnreg.inc.sync.aligned.u32 240;");
    const int h = wg, w = warp & 3;
    const int gq = lane >> 2, t = lane & 3;
    const int ghw = (g * 2 + h) * 4 + w;


    if (h == 0) { release(4); release(5); }
    Stager stg{sbase + OFF_STG + warp * STG_BYTES, bars + 8 * (BAR_STG + warp), 0u, lane};
    int slot = 0;
    uint32_t phase = 0;
    auto stage_wait = [&]() -> uint32_t {
        mbar_wait(bars + 8 * (BAR_FULL + slot), phase);
        return sbase + slot * STAGE;
    };
    auto stage_next = [&]() { if (++slot == NSTAGE) { slot = 0; phase ^= 1; } };
    auto prev_slot = [&]() -> int { return slot == 0 ? NSTAGE - 1 : slot - 1; };

    uint32_t xa[28][4];
    uint4 xres[4];
#pragma unroll
    for (int m = 0; m < 4; m++) xres[m] = make_uint4(0, 0, 0, 0);
    RowScale sc0, sc1;
    uint32_t epoch, tag, tag3;
    {
        const uint32_t xbar = bars + 8 * (BAR_X + 7 * h);
        const uint32_t xrow = sbase + (h ? OFF_XB : OFF_STG) + (16 * w + (lane & 7) + ((lane >> 3) & 1) * 8) * 128;
        uint32_t xsw[4];
#pragma unroll
        for (int m = 0; m < 4; m++) xsw[m] = xrow + (((2 * m + (lane >> 4)) ^ (lane & 7)) << 4);
        {
            float s0 = 0.f, q0 = 0.f, s1 = 0.f, q1 = 0.f;
#pragma unroll 1
            for (int a = 0; a < 7; a++) {
                mbar_wait(xbar + 8 * a, 0);
                uint4 r[4];
#pragma unroll
                for (int m = 0; m < 4; m++) {
                    uint32_t q[4];
                    ldsm4(q, xsw[m] + a * XATOM);
                    r[m] = make_uint4(q[0], q[1], q[2], q[3]);
                }
                accum_stats(r, s0, q0, s1, q1);
                if (a == j) {
#pragma unroll
                    for (int m = 0; m < 4; m++) xres[m] = r[m];
                }
            }
            quad_reduce(s0, q0, s1, q1);
            float rs0, mr0, rs1, mr1;
            stats_to_scale(s0, q0, s1, q1, rs0, mr0, rs1, mr1);
            sc0.set(rs0, mr0);
            sc1.set(rs1, mr1);
        }
        asm volatile("add.u32 %0, %1, 1;" : "=r"(epoch) : "r"(epoch_raw));
        tag = epoch & 1u;
        tag3 = 1 + epoch % 3u;
#pragma unroll
        for (int a = 0; a < 7; a++) {
#pragma unroll
            for (int m = 0; m < 4; m++) ldsm4(xa[4 * a + m], xsw[m] + a * XATOM);
        }
        if (h == 1) { release(4); release(5); }
        else { __syncwarp(); if (lane == 0) mbar_arrive(bars + 8 * BAR_XREAD); }
    }
    auto qkv_pass = [&](uint32_t (&lo)[7], uint32_t (&hi)[7], bool first, auto&& between) {
        float acc[28];
#pragma unroll
        for (int st = 0; st < 2; st++) {
            if (first) {
#pragma unroll
                for (int u = 0; u < 14; u++) {
                    const int ks = 14 * st + u;
                    xa[ks][0] = sc0.apply(xa[ks][0]); xa[ks][1] = sc1.apply(xa[ks][1]);
                    xa[ks][2] = sc0.apply(xa[ks][2]); xa[ks][3] = sc1.apply(xa[ks][3]);
                }
            }
            const uint64_t d = make_desc(stage_wait());
            wg_fence();
#pragma unroll
            for (int m = 0; m < 14; m++) {
                const int ks = 14 * st + m;
                wgmma_rs_n56(acc, xa[ks][0], xa[ks][1], xa[ks][2], xa[ks][3], d + m * 128, ks > 0);
            }
            wg_commit();
            if (st > 0) { wg_wait<1>(); release(prev_slot()); }
            stage_next();
        }
        between();
        wg_wait<0>();
        keep_regs(acc);
        release(prev_slot());
#pragma unroll
        for (int i = 0; i < 7; i++) {
            lo[i] = pack_bf16(acc[4 * i], acc[4 * i + 1]);
            hi[i] = pack_bf16(acc[4 * i + 2], acc[4 * i + 3]);
        }
    };
    const bool has_prev = (w > 0) || (g > 0);
    uint4* const halo_out = &g_halo[((g * 2 + h) * 8 + j) * 128 + lane];
    const uint4* const halo_in = &g_halo[(((g - 1) * 2 + h) * 8 + j) * 128 + lane];
    const uint32_t next_stg = stg.buf + STG_BYTES + lane * 16;
    uint32_t kL[7], kU[7], vL[7], vU[7], qL[7], qU[7];
    qkv_pass(kL, kU, true, []() {});
    mbar_wait(bars + 8 * BAR_XREAD, 0);
    if (w < 3) {
        sts128(next_stg, kU[0], kU[1], kU[2], kU[3]);
        sts128(next_stg + 512, 0u, kU[4], kU[5], kU[6]);
        bar_arrive(1 + h * 3 + w, 64);
    } else if (g < 15) {
        st_ll(halo_out, set_tag(kU[0], tag), kU[1], kU[2], kU[3]);
        st_ll(halo_out + 32, tag, kU[4], kU[5], kU[6]);
    }
    uint4 hk[2], hv[2];
    hk[0] = hk[1] = hv[0] = hv[1] = make_uint4(0, 0, 0, 0);
#pragma unroll
    for (int i = 0; i < 7; i++) vL[i] = vU[i] = 0;
#pragma unroll 1
    for (int ps = 0; ps < 2; ps++) {
        if (ps == 1) {
            if (w > 0) {
                bar_sync(1 + h * 3 + w - 1, 64);
                hk[0] = lds128(stg.buf + lane * 16); hk[1] = lds128(stg.buf + 512 + lane * 16);
            } else if (g > 0) {
                hk[0] = ld_ll(halo_in); hk[1] = ld_ll(halo_in + 32);
            }
        }
        qkv_pass(qL, qU, false, [&]() {
            if (ps == 1) {
                if (w > 0) {
                    bar_sync(7 + h * 3 + w - 1, 64);
                    hv[0] = lds128(stg.buf + 1024 + lane * 16); hv[1] = lds128(stg.buf + 1536 + lane * 16);
                } else if (g > 0) {
                    hv[0] = ld_ll(halo_in + 64); hv[1] = ld_ll(halo_in + 96);
                }
            }
        });
        if (ps == 0) {
            if (w < 3) {
                sts128(next_stg + 1024, qU[0], qU[1], qU[2], qU[3]);
                sts128(next_stg + 1536, 0u, qU[4], qU[5], qU[6]);
                bar_arrive(7 + h * 3 + w, 64);
            } else if (g < 15) {
                st_ll(halo_out + 64, set_tag(qU[0], tag), qU[1], qU[2], qU[3]);
                st_ll(halo_out + 96, tag, qU[4], qU[5], qU[6]);
            }
#pragma unroll
            for (int i = 0; i < 7; i++) { vL[i] = movtrans(qL[i]); vU[i] = movtrans(qU[i]); }
        }
    }
    if (h == 1) {
        const long long t0 = clock64();
        while (clock64() - t0 < ODD_DELAY) {}
    }
    const bool remote_prev = (w == 0) && (g > 0);
    if (remote_prev) validate<2, 32>(hk, halo_in, tag);
    uint32_t oL[7], oU[7];
    {
        const uint32_t kH[7] = {hk[0].x, hk[0].y, hk[0].z, hk[0].w, hk[1].y, hk[1].z, hk[1].w};
        uint32_t vHt[7];
        const bool up0 = 2 * t > gq, up1 = 2 * t + 1 > gq;
        const uint32_t upmask = (up0 ? 0xffffu : 0u) | (up1 ? 0xffff0000u : 0u);
        const float sc = 0.18898223650461362f * 1.4426950408889634f;
        float oh[2][4][4];
        uint32_t pk[2][4];
#pragma unroll
        for (int hd = 0; hd < 2; hd++) {
            const int b0 = 3 * hd;
            uint32_t aL[4], aU[4];
#pragma unroll
            for (int i = 0; i < 4; i++) { aL[i] = qL[b0 + i]; aU[i] = qU[b0 + i]; }
            if (hd == 0) { if (t >= 2) { aL[3] = 0; aU[3] = 0; } } else { if (t < 2) { aL[0] = 0; aU[0] = 0; } }
            float sH[4] = {0.f, 0.f, 0.f, 0.f}, sL[4] = {0.f, 0.f, 0.f, 0.f}, sU[4] = {0.f, 0.f, 0.f, 0.f};
            mma16816(sH, aL[0], aU[0], aL[1], aU[1], kH[b0], kH[b0 + 1]);
            mma16816(sL, aL[0], aU[0], aL[1], aU[1], kL[b0], kL[b0 + 1]);
            mma16816(sU, aL[0], aU[0], aL[1], aU[1], kU[b0], kU[b0 + 1]);
            mma16816(sH, aL[2], aU[2], aL[3], aU[3], kH[b0 + 2], kH[b0 + 3]);
            mma16816(sL, aL[2], aU[2], aL[3], aU[3], kL[b0 + 2], kL[b0 + 3]);
            mma16816(sU, aL[2], aU[2], aL[3], aU[3], kU[b0 + 2], kU[b0 + 3]);
            const float ninf = __int_as_float(0xff800000);
            float a0 = up0 ? (has_prev ? sH[0] : ninf) : sL[0];
            float a1 = up1 ? (has_prev ? sH[1] : ninf) : sL[1];
            float c0 = up0 ? sL[2] : sU[2];
            float c1 = up1 ? sL[3] : sU[3];
            float ma = fmaxf(a0, a1), mc = fmaxf(c0, c1);
            ma = fmaxf(ma, __shfl_xor_sync(0xffffffffu, ma, 1));
            mc = fmaxf(mc, __shfl_xor_sync(0xffffffffu, mc, 1));
            ma = fmaxf(ma, __shfl_xor_sync(0xffffffffu, ma, 2));
            mc = fmaxf(mc, __shfl_xor_sync(0xffffffffu, mc, 2));
            a0 = ex2((a0 - ma) * sc); a1 = ex2((a1 - ma) * sc);
            c0 = ex2((c0 - mc) * sc); c1 = ex2((c1 - mc) * sc);
            float sa = a0 + a1, scs = c0 + c1;
            sa += __shfl_xor_sync(0xffffffffu, sa, 1);
            scs += __shfl_xor_sync(0xffffffffu, scs, 1);
            sa += __shfl_xor_sync(0xffffffffu, sa, 2);
            scs += __shfl_xor_sync(0xffffffffu, scs, 2);
            const float ia = __fdividef(1.0f, sa), ic = __fdividef(1.0f, scs);
            a0 *= ia; a1 *= ia; c0 *= ic; c1 *= ic;
            const uint32_t pa = pack_bf16(a0, a1), pc = pack_bf16(c0, c1);
            pk[hd][0] = pa & upmask;
            pk[hd][1] = pa & ~upmask;
            pk[hd][2] = pc & upmask;
            pk[hd][3] = pc & ~upmask;
        }
        if (remote_prev) validate<2, 32>(hv, halo_in + 64, tag);
        {
            const uint32_t vH[7] = {hv[0].x, hv[0].y, hv[0].z, hv[0].w, hv[1].y, hv[1].z, hv[1].w};
#pragma unroll
            for (int i = 0; i < 7; i++) vHt[i] = movtrans(vH[i]);
        }
#pragma unroll
        for (int hd = 0; hd < 2; hd++) {
#pragma unroll
            for (int i = 0; i < 4; i++) {
                oh[hd][i][0] = oh[hd][i][1] = oh[hd][i][2] = oh[hd][i][3] = 0.f;
                mma16816(oh[hd][i], pk[hd][0], 0u, pk[hd][1], pk[hd][2], vHt[3 * hd + i], vL[3 * hd + i]);
                mma1688(oh[hd][i], 0u, pk[hd][3], vU[3 * hd + i]);
            }
        }
#pragma unroll
        for (int i = 0; i < 7; i++) {
            float o4[4];
#pragma unroll
            for (int e = 0; e < 4; e++)
                o4[e] = i < 3 ? oh[0][i][e] : (i > 3 ? oh[1][i - 3][e] : (t < 2 ? oh[0][3][e] : oh[1][0][e]));
            oL[i] = pack_bf16(o4[0], o4[1]);
            oU[i] = pack_bf16(o4[2], o4[3]);
        }
    }
    {
        uint4* row = &g_x1[ghw * 28 * 32 + lane];
        const int k0 = (7 * j + 1) >> 1;
        const bool odd = j & 1;
        st_ll(row + k0 * 32, set_tag(odd ? oL[1] : oL[0], tag), odd ? oU[1] : oU[0], odd ? oL[2] : oL[1], odd ? oU[2] : oU[1]);
        st_ll(row + (k0 + 1) * 32, set_tag(odd ? oL[3] : oL[2], tag), odd ? oU[3] : oU[2], odd ? oL[4] : oL[3], odd ? oU[4] : oU[3]);
        st_ll(row + (k0 + 2) * 32, set_tag(odd ? oL[5] : oL[4], tag), odd ? oU[5] : oU[4], odd ? oL[6] : oL[5], odd ? oU[6] : oU[5]);
        st_ll8(reinterpret_cast<uint8_t*>(row + (odd ? k0 - 1 : k0 + 3) * 32) + (odd ? 8 : 0),
               set_tag(odd ? oL[0] : oL[6], tag), odd ? oU[0] : oU[6]);
        if (lane == 0) st_rlx(&g_hint1[ghw * 8 + j], epoch);
    }
    long long t_pub = clock64();
    constexpr uint32_t X1_HALVES = (1u << 3) | (1u << 10);
    long long t_st = 0;
    uint4 hr[4];
#pragma unroll
    for (int m = 0; m < 4; m++) hr[m] = make_uint4(0, 0, 0, 0);
    if (j < 7) {
        const uint4* src = &g_x1[ghw * 28 * 32];
        while (clock64() - t_pub < FETCH_DELAY_O) {}
        stg.fetch(src, STG_BYTES);
        uint4 v[28];
        float acc[32];
        stg.take_retry<0, 14, X1_HALVES, 8>(v, src, tag, &g_hint1[ghw * 8], epoch);
        stg.fetch(src + 14 * 32, STG_BYTES);
#pragma unroll
        for (int st = 0; st < 2; st++) {
            if (st == 1) stg.take_retry<14, 14, X1_HALVES>(v, src + 14 * 32, tag);
            const uint64_t d = make_desc(stage_wait());
            wg_fence();
#pragma unroll
            for (int m = 0; m < 14; m++) {
                const int ks = 14 * st + m;
                wgmma_rs_n64(acc, v[ks].x, v[ks].y, v[ks].z, v[ks].w, d + m * 128, ks > 0);
            }
            wg_commit();
            if (st > 0) { wg_wait<1>(); release(prev_slot()); }
            stage_next();
        }
        wg_wait<0>();
        keep_regs(acc);
        release(prev_slot());
        uint4* dst = &g_x2[(ghw * 28 + 4 * j) * 32 + lane];
#pragma unroll
        for (int m = 0; m < 4; m++) {
            const uint4 xr = xres[m];
            acc[8 * m] += bf_lo(xr.x); acc[8 * m + 1] += bf_hi(xr.x); acc[8 * m + 2] += bf_lo(xr.y); acc[8 * m + 3] += bf_hi(xr.y);
            acc[8 * m + 4] += bf_lo(xr.z); acc[8 * m + 5] += bf_hi(xr.z); acc[8 * m + 6] += bf_lo(xr.w); acc[8 * m + 7] += bf_hi(xr.w);
            hr[m].x = pack_bf16(acc[8 * m], acc[8 * m + 1]);
            hr[m].y = pack_bf16(acc[8 * m + 2], acc[8 * m + 3]);
            hr[m].z = pack_bf16(acc[8 * m + 4], acc[8 * m + 5]);
            hr[m].w = pack_bf16(acc[8 * m + 6], acc[8 * m + 7]);
            st_ll(dst + m * 32, set_tag(hr[m].x, tag), hr[m].y, hr[m].z, hr[m].w);
        }
        t_pub = clock64();
        {
            float s0 = 0.f, q0 = 0.f, s1 = 0.f, q1 = 0.f;
#pragma unroll
            for (int i = 0; i < 8; i++) {
                s0 += acc[4 * i] + acc[4 * i + 1]; q0 = fmaf(acc[4 * i], acc[4 * i], fmaf(acc[4 * i + 1], acc[4 * i + 1], q0));
                s1 += acc[4 * i + 2] + acc[4 * i + 3]; q1 = fmaf(acc[4 * i + 2], acc[4 * i + 2], fmaf(acc[4 * i + 3], acc[4 * i + 3], q1));
            }
            quad_reduce(s0, q0, s1, q1);
            if (t == 0) st_ll(&g_st2[(((g * 2 + h) * 7 + j) * 4 + w) * 8 + gq], (__float_as_uint(s0) & ~3u) | tag3,
                              __float_as_uint(q0), __float_as_uint(s1), __float_as_uint(q1));
        }
        if (lane == 0) st_rlx(&g_hint2[ghw * 8 + j], epoch);
        t_st = clock64();
    }
    uint32_t h1[14][4];
    {
        const uint4* const hsrc = &g_x2[ghw * 28 * 32];
        if (j < 7) { while (clock64() - t_pub < FETCH_DELAY_H) {} }
        else wait_hints(&g_hint2[ghw * 8], 7, epoch, lane);
        stg.fetch(hsrc, STG_BYTES);
        uint4 v[28];
        const uint4* ssrc = &g_st2[((g * 2 + h) * 7 * 4 + w) * 8 + gq];
        uint4 sv[7];
        if (j < 7) { while (clock64() - t_st < FETCH_DELAY_S) {} }
#pragma unroll
        for (int i = 0; i < 7; i++) sv[i] = ld_ll(ssrc + i * 32);
        {
            float acc[64];
#pragma unroll
            for (int st = 0; st < 4; st++) {
                if (st == 0) {
                    stg.take_retry<0, 14, 0u, 7>(v, hsrc, tag, &g_hint2[ghw * 8], epoch);
                    stg.fetch(hsrc + 14 * 32, STG_BYTES);
                    float rs0, mr0, rs1, mr1;
                    finish_stats(sv, ssrc, tag3, rs0, mr0, rs1, mr1);
                    sc0.set(rs0, mr0);
                    sc1.set(rs1, mr1);
                }
                if (st == 2) {
                    stg.take_retry<14, 14, 0u>(v, hsrc + 14 * 32, tag);
#pragma unroll
                    for (int m = 0; m < 4; m++) sts128(stg.buf + 4096 + m * 512 + lane * 16, hr[m].x, hr[m].y, hr[m].z, hr[m].w);
                }
#pragma unroll
                for (int m = 0; m < 7; m++) {
                    const int ks = 7 * st + m;
                    v[ks].x = sc0.apply(v[ks].x); v[ks].y = sc1.apply(v[ks].y);
                    v[ks].z = sc0.apply(v[ks].z); v[ks].w = sc1.apply(v[ks].w);
                }
                const uint64_t d = make_desc(stage_wait());
                wg_fence();
#pragma unroll
                for (int m = 0; m < 7; m++) {
                    const int ks = 7 * st + m;
                    wgmma_rs_n128(acc, v[ks].x, v[ks].y, v[ks].z, v[ks].w, d + m * 128, ks > 0);
                }
                wg_commit();
                if (st > 0) { wg_wait<1>(); release(prev_slot()); }
                stage_next();
            }
            wg_wait<0>();
            keep_regs(acc);
            release(prev_slot());
#pragma unroll
            for (int i = 0; i < 16; i++) {
                h1[i >> 1][(i & 1) * 2] = pack_relu_bf16(acc[4 * i], acc[4 * i + 1]);
                h1[i >> 1][(i & 1) * 2 + 1] = pack_relu_bf16(acc[4 * i + 2], acc[4 * i + 3]);
            }
        }
        {
            float acc[48];
#pragma unroll
            for (int st = 0; st < 4; st++) {
                const uint64_t d = make_desc(stage_wait());
                wg_fence();
#pragma unroll
                for (int m = 0; m < 7; m++) {
                    const int ks = 7 * st + m;
                    wgmma_rs_n96(acc, v[ks].x, v[ks].y, v[ks].z, v[ks].w, d + m * 128, ks > 0);
                }
                wg_commit();
                if (st > 0) { wg_wait<1>(); release(prev_slot()); }
                stage_next();
            }
            wg_wait<0>();
            keep_regs(acc);
            release(prev_slot());
#pragma unroll
            for (int i = 0; i < 12; i++) {
                h1[8 + (i >> 1)][(i & 1) * 2] = pack_relu_bf16(acc[4 * i], acc[4 * i + 1]);
                h1[8 + (i >> 1)][(i & 1) * 2 + 1] = pack_relu_bf16(acc[4 * i + 2], acc[4 * i + 3]);
            }
        }
    }
    {
        float acc[32], sum[32];
        auto add_partial = [&](const uint4& u, int m) {
            sum[8 * m] += bf_lo(u.x); sum[8 * m + 1] += bf_hi(u.x);
            sum[8 * m + 2] += bf_lo(u.y); sum[8 * m + 3] += bf_hi(u.y);
            sum[8 * m + 4] += bf_lo(u.z); sum[8 * m + 5] += bf_hi(u.z);
            sum[8 * m + 6] += bf_lo(u.w); sum[8 * m + 7] += bf_hi(u.w);
        };
#pragma unroll
        for (int m = 0; m < 4; m++) {
            const uint4 u = lds128(stg.buf + 4096 + m * 512 + lane * 16);
            sum[8 * m] = bf_lo(u.x); sum[8 * m + 1] = bf_hi(u.x); sum[8 * m + 2] = bf_lo(u.y); sum[8 * m + 3] = bf_hi(u.y);
            sum[8 * m + 4] = bf_lo(u.z); sum[8 * m + 5] = bf_hi(u.z); sum[8 * m + 6] = bf_lo(u.w); sum[8 * m + 7] = bf_hi(u.w);
        }
        int ghw5 = ghw, j5 = j;
        asm volatile("" : "+r"(ghw5), "+r"(j5));
        const uint4* const mine = &g_x3[(ghw5 * 7 + j5) * 8 * 128];
        const uint4* pending = mine;
        int blk = (j < 7) ? j : gp + 6;
        int srcr = j;
#pragma unroll 1
        for (int pss = 0; pss < 7; pss++) {
            blk = blk >= 6 ? blk - 6 : blk + 1;
            if (blk >= 7) blk -= 7;
            const uint64_t d = make_desc(stage_wait());
            wg_fence();
#pragma unroll
            for (int m = 0; m < 14; m++)
                wgmma_rs_n64(acc, h1[m][0], h1[m][1], h1[m][2], h1[m][3], d + m * 128, m > 0);
            wg_commit();
            if (j < 7) {
                if (pss >= 3) {
                    uint4 u[4];
                    stg.take_retry<0, 4, 0u>(u, pending, tag);
#pragma unroll
                    for (int m = 0; m < 4; m++) add_partial(u[m], m);
                }
                if (pss >= 2) {
                    srcr = srcr == 0 ? 6 : srcr - 1;
                    pending = mine + srcr * 128;
                    stg.fetch(pending, 2048);
                }
            }
            wg_wait<0>();
            keep_regs(acc);
            if (pss < 7 - NSTAGE) release(slot);
            if (pss < 6 || j == 7) {
                uint4* dst = &g_x3[((ghw5 * 7 + blk) * 8 + j5) * 128 + lane];
#pragma unroll
                for (int m = 0; m < 4; m++)
                    st_ll(dst + m * 32, set_tag(pack_bf16(acc[8 * m], acc[8 * m + 1]), tag), pack_bf16(acc[8 * m + 2], acc[8 * m + 3]),
                          pack_bf16(acc[8 * m + 4], acc[8 * m + 5]), pack_bf16(acc[8 * m + 6], acc[8 * m + 7]));
            }
            stage_next();
        }
        if (j < 7) {
            srcr = srcr == 0 ? 6 : srcr - 1;
            const uint4* pa = mine + srcr * 128;
            const uint4* pb = mine + 7 * 128;
            uint4 u[8];
            stg.take_retry<0, 4, 0u>(u, pending, tag);
            stg.fetch2(pa, pb);
#pragma unroll
            for (int m = 0; m < 4; m++) add_partial(u[m], m);
#pragma unroll 1
            for (int it = 0; it < SPIN_LIMIT; it++) {
                if (stg.take<0, 8, 0u>(u, tag)) break;
                stg.fetch2(pa, pb);
            }
#pragma unroll
            for (int m = 0; m < 8; m++) add_partial(u[m], m & 3);
            __syncwarp();
            const uint32_t tile = stg.buf + 4096;
#pragma unroll
            for (int m = 0; m < 4; m++) {
                const int r = (lane & 7) + ((lane >> 3) & 1) * 8, ch = 2 * m + (lane >> 4);
                stsm4(tile + r * 128 + ((ch ^ (r & 7)) << 4),
                      pack_bf16(sum[8 * m] + acc[8 * m], sum[8 * m + 1] + acc[8 * m + 1]),
                      pack_bf16(sum[8 * m + 2] + acc[8 * m + 2], sum[8 * m + 3] + acc[8 * m + 3]),
                      pack_bf16(sum[8 * m + 4] + acc[8 * m + 4], sum[8 * m + 5] + acc[8 * m + 5]),
                      pack_bf16(sum[8 * m + 6] + acc[8 * m + 6], sum[8 * m + 7] + acc[8 * m + 7]));
            }
            __syncwarp();
#pragma unroll
            for (int q = 0; q < 4; q++) {
                const int r = 4 * q + (lane >> 3), ch = lane & 7;
                const uint4 o4 = lds128(tile + r * 128 + ((ch ^ (r & 7)) << 4));
                *reinterpret_cast<uint4*>(out + (size_t)(128 * g + 32 * w + 2 * r + h) * DM + 64 * j + 8 * ch) = o4;
            }
        }
    }
    if (tid == 0) g_epoch[b] = epoch;
}

namespace {

template <bool LN, bool RELU, bool RES>
__global__ void __launch_bounds__(256) plain_gemm(const __nv_bfloat16* __restrict__ A, const __nv_bfloat16* __restrict__ W,
                                                  const __nv_bfloat16* __restrict__ R, __nv_bfloat16* __restrict__ C,
                                                  int N, int K) {
    __shared__ float sa[64][33], sb[32][65], srs[64], smean[64];
    const int tid = threadIdx.x, row0 = blockIdx.y * 64, col0 = blockIdx.x * 64;
    if (LN) {
        const int r = tid >> 2, q = tid & 3;
        float s = 0.f, ss = 0.f;
        for (int k = q; k < K; k += 4) { const float v = __bfloat162float(A[(size_t)(row0 + r) * K + k]); s += v; }
        s += __shfl_xor_sync(0xffffffffu, s, 1);
        s += __shfl_xor_sync(0xffffffffu, s, 2);
        const float m = s / K;
        for (int k = q; k < K; k += 4) { const float v = __bfloat162float(A[(size_t)(row0 + r) * K + k]) - m; ss += v * v; }
        ss += __shfl_xor_sync(0xffffffffu, ss, 1);
        ss += __shfl_xor_sync(0xffffffffu, ss, 2);
        if (q == 0) { smean[r] = m; srs[r] = rsqrtf(ss / K + LN_EPS); }
        __syncthreads();
    }
    const int tr = (tid >> 4) * 4, tc = (tid & 15) * 4;
    float acc[4][4] = {};
    for (int k0 = 0; k0 < K; k0 += 32) {
        for (int i = tid; i < 64 * 32; i += 256) {
            const int r = i >> 5, k = i & 31;
            float v = __bfloat162float(A[(size_t)(row0 + r) * K + k0 + k]);
            if (LN) v = __bfloat162float(__float2bfloat16((v - smean[r]) * srs[r]));
            sa[r][k] = v;
        }
        for (int i = tid; i < 32 * 64; i += 256) {
            const int k = i >> 6, c = i & 63;
            sb[k][c] = __bfloat162float(W[(size_t)(k0 + k) * N + col0 + c]);
        }
        __syncthreads();
        for (int k = 0; k < 32; k++) {
#pragma unroll
            for (int a = 0; a < 4; a++)
#pragma unroll
                for (int c = 0; c < 4; c++) acc[a][c] = fmaf(sa[tr + a][k], sb[k][tc + c], acc[a][c]);
        }
        __syncthreads();
    }
#pragma unroll
    for (int a = 0; a < 4; a++)
#pragma unroll
        for (int c = 0; c < 4; c++) {
            const size_t o = (size_t)(row0 + tr + a) * N + col0 + tc + c;
            float v = acc[a][c];
            if (RELU) v = fmaxf(v, 0.f);
            if (RES) v += __bfloat162float(R[o]);
            C[o] = __float2bfloat16(v);
        }
}
__global__ void __launch_bounds__(256) plain_attention(const __nv_bfloat16* __restrict__ qkv, __nv_bfloat16* __restrict__ o) {
    const int i = blockIdx.x * 256 + threadIdx.x, s = i >> 4, hd = i & 15;
    const __nv_bfloat16* q = qkv + (size_t)s * NQKV + hd * 28;
    float lg[8], mx = -INFINITY;
    for (int w = 0; w < 8; w++) {
        lg[w] = -INFINITY;
        if (s - 2 * w >= 0) {
            const __nv_bfloat16* k = qkv + (size_t)(s - 2 * w) * NQKV + DM + hd * 28;
            float d = 0.f;
            for (int e = 0; e < 28; e++) d = fmaf(__bfloat162float(q[e]), __bfloat162float(k[e]), d);
            lg[w] = d * 0.18898223650461362f;
        }
        mx = fmaxf(mx, lg[w]);
    }
    float sum = 0.f;
    for (int w = 0; w < 8; w++) { lg[w] = __expf(lg[w] - mx); sum += lg[w]; }
    for (int e = 0; e < 28; e++) {
        float a = 0.f;
        for (int w = 0; w < 8; w++)
            if (s - 2 * w >= 0)
                a = fmaf(__bfloat162float(__float2bfloat16(lg[w] / sum)),
                         __bfloat162float(qkv[(size_t)(s - 2 * w) * NQKV + 2 * DM + hd * 28 + e]), a);
        o[(size_t)s * DM + hd * 28 + e] = __float2bfloat16(a);
    }
}
__device__ __nv_bfloat16 g_plain[2048 * (NQKV + DM + DM + DFF)];

void plain_launch(const __nv_bfloat16* x, const __nv_bfloat16* wqkv, const __nv_bfloat16* wo, const __nv_bfloat16* w1,
                  const __nv_bfloat16* w2, __nv_bfloat16* out) {
    void* base = nullptr;
    cudaGetSymbolAddress(&base, g_plain);
    __nv_bfloat16* qkv = (__nv_bfloat16*)base;
    __nv_bfloat16* o = qkv + 2048 * NQKV;
    __nv_bfloat16* h = o + 2048 * DM;
    __nv_bfloat16* h1 = h + 2048 * DM;
    cudaStream_t st = cudaStreamPerThread;
    plain_gemm<true, false, false><<<dim3(NQKV / 64, 32), 256, 0, st>>>(x, wqkv, nullptr, qkv, NQKV, DM);
    plain_attention<<<2048 * 16 / 256, 256, 0, st>>>(qkv, o);
    plain_gemm<false, false, true><<<dim3(DM / 64, 32), 256, 0, st>>>(o, wo, x, h, DM, DM);
    plain_gemm<true, true, false><<<dim3(DFF / 64, 32), 256, 0, st>>>(h, w1, nullptr, h1, DFF, DM);
    plain_gemm<false, false, true><<<dim3(DM / 64, 32), 256, 0, st>>>(h1, w2, h, out, DM, DFF);
}

}

typedef CUresult (*EncodeTiledFn)(CUtensorMap*, CUtensorMapDataType, cuuint32_t, void*, const cuuint64_t*,
                                  const cuuint64_t*, const cuuint32_t*, const cuuint32_t*, CUtensorMapInterleave,
                                  CUtensorMapSwizzle, CUtensorMapL2promotion, CUtensorMapFloatOOBfill);

static void encode2d(EncodeTiledFn enc, CUtensorMap* m, const void* base, int cols, int rows, int box_cols, int box_rows) {
    cuuint64_t dims[2] = {(cuuint64_t)cols, (cuuint64_t)rows};
    cuuint64_t strides[1] = {(cuuint64_t)cols * 2};
    cuuint32_t box[2] = {(cuuint32_t)box_cols, (cuuint32_t)box_rows};
    cuuint32_t es[2] = {1, 1};
    enc(m, CU_TENSOR_MAP_DATA_TYPE_BFLOAT16, 2, const_cast<void*>(base), dims, strides, box, es,
        CU_TENSOR_MAP_INTERLEAVE_NONE, CU_TENSOR_MAP_SWIZZLE_128B, CU_TENSOR_MAP_L2_PROMOTION_L2_64B,
        CU_TENSOR_MAP_FLOAT_OOB_FILL_NONE);
}

extern "C" void kernel_launch(void* const* d_in, const int* in_sizes, int n_in, void* d_out, int out_size) {
    (void)in_sizes; (void)n_in; (void)out_size;
    const __nv_bfloat16* x = (const __nv_bfloat16*)d_in[0];
    const __nv_bfloat16* wqkv = (const __nv_bfloat16*)d_in[1];
    const __nv_bfloat16* wo = (const __nv_bfloat16*)d_in[2];
    const __nv_bfloat16* w1 = (const __nv_bfloat16*)d_in[4];
    const __nv_bfloat16* w2 = (const __nv_bfloat16*)d_in[5];

    static EncodeTiledFn enc = nullptr;
    static int fused_ok = -1;
    if (fused_ok < 0) {
        cudaDriverEntryPointQueryResult qr;
        void* fn = nullptr;
        cudaGetDriverEntryPoint("cuTensorMapEncodeTiled", &fn, cudaEnableDefault, &qr);
        enc = (EncodeTiledFn)fn;
        int dev = 0, sms = 0, per_sm = 0;
        cudaGetDevice(&dev);
        cudaDeviceGetAttribute(&sms, cudaDevAttrMultiProcessorCount, dev);
        const cudaError_t e = cudaFuncSetAttribute(fused_block_kernel, cudaFuncAttributeMaxDynamicSharedMemorySize, SMEM_BYTES);
        if (e == cudaSuccess) cudaOccupancyMaxActiveBlocksPerMultiprocessor(&per_sm, fused_block_kernel, 384, SMEM_BYTES);
        fused_ok = (enc != nullptr && e == cudaSuccess && sms * per_sm >= GRID) ? 1 : 0;
        (void)cudaGetLastError();
    }
    if (!fused_ok) {
        plain_launch(x, wqkv, wo, w1, w2, (__nv_bfloat16*)d_out);
        return;
    }
    CUtensorMap m_x, m_qkv, m_wo, m_w1, m_w1h, m_w2a, m_w2b;
    {
        cuuint64_t dims[3] = {DM, 1024, 2};
        cuuint64_t strides[2] = {DM * 4, DM * 2};
        cuuint32_t box[3] = {64, 64, 1};
        cuuint32_t es[3] = {1, 1, 1};
        enc(&m_x, CU_TENSOR_MAP_DATA_TYPE_BFLOAT16, 3, const_cast<__nv_bfloat16*>(x), dims, strides, box, es,
            CU_TENSOR_MAP_INTERLEAVE_NONE, CU_TENSOR_MAP_SWIZZLE_128B, CU_TENSOR_MAP_L2_PROMOTION_L2_64B,
            CU_TENSOR_MAP_FLOAT_OOB_FILL_NONE);
    }
    encode2d(enc, &m_qkv, wqkv, NQKV, DM, 56, 112);
    encode2d(enc, &m_wo, wo, DM, DM, 64, 112);
    encode2d(enc, &m_w1, w1, DFF, DM, 64, 112);
    encode2d(enc, &m_w1h, w1, DFF, DM, 32, 112);
    encode2d(enc, &m_w2a, w2, DM, DFF, 64, 96);
    encode2d(enc, &m_w2b, w2, DM, DFF, 64, 32);

    cudaLaunchConfig_t cfg = {};
    cfg.gridDim = dim3(GRID);
    cfg.blockDim = dim3(384);
    cfg.dynamicSmemBytes = SMEM_BYTES;
    cfg.stream = cudaStreamPerThread;
    cudaLaunchKernelEx(&cfg, fused_block_kernel, m_x, m_qkv, m_wo, m_w1, m_w1h, m_w2a, m_w2b,
                       (__nv_bfloat16*)d_out);
}
```
